```python
import torch

def _softmax(x, axis=-1):
    return torch.softmax(x, dim=axis)
def _gelu(x):
    return torch.nn.functional.gelu(x, approximate="tanh")
def _silu(x):
    return torch.nn.functional.silu(x)
def _sigmoid(x):
    return torch.sigmoid(x)
def _layernorm(x, axis=-1, eps=1e-5):
    m = x.mean(dim=axis, keepdim=True)
    v = x.var(dim=axis, keepdim=True, unbiased=False)
    return (x - m) / torch.sqrt(v + eps)
def _scatter_add(tgt, idx, src, axis=0):
    return tgt.clone().index_add_(axis, idx, src)
def _segment_sum(src, seg, n):
    out = torch.zeros((n,) + src.shape[1:], dtype=src.dtype)
    return out.index_add_(0, seg, src)
def _pad(x, pw):
    flat = tuple(v for pair in reversed(pw) for v in pair)
    return torch.nn.functional.pad(x, flat)

kernel_name = 'gated_mix__mha_block__dense_activation_squared_relu__prompt'

def setup_inputs():

    _w = (lambda a: (lambda t: t.to(torch.bfloat16) if t.is_floating_point() else t)(torch.as_tensor(a)))
    def _A_setup():
        B, S, D, H = 1, 2048, 640, 32
        return {
            "x": _w((lambda *s: torch.randn(*s, dtype=torch.bfloat16) * 0.05)(B, S, D)),
            "wqkv": _w((lambda *s: torch.randn(*s, dtype=torch.bfloat16) * 0.8)(D, 3 * D)),
            "wo": _w((lambda *s: torch.randn(*s, dtype=torch.bfloat16) * 0.1)(D, D)),
        }
    _A_in = _A_setup()

    def _B_setup():
        B, S, D, F = 1, 2048, 640, 1728
        return {
            "x": _w((lambda *s: torch.randn(*s, dtype=torch.bfloat16) * 0.05)(B, S, D)),
            "w1": _w((lambda *s: torch.randn(*s, dtype=torch.bfloat16) * 0.1)(D, F)),
            "b1": _w((lambda *s: torch.randn(*s, dtype=torch.bfloat16) * 0.1)(F)),
            "w2": _w((lambda *s: torch.randn(*s, dtype=torch.bfloat16) * 0.1)(F, D)),
            "b2": _w((lambda *s: torch.randn(*s, dtype=torch.bfloat16) * 0.05)(D)),
        }
    _B_in = _B_setup()

    return {
        "A_x": _A_in["x"],
        "A_wqkv": _A_in["wqkv"],
        "A_wo": _A_in["wo"],
        "B_x": _B_in["x"],
        "B_w1": _B_in["w1"],
        "B_b1": _B_in["b1"],
        "B_w2": _B_in["w2"],
        "B_b2": _B_in["b2"],
        "gate_w": _w((lambda *s: torch.randn(*s, dtype=torch.bfloat16) * 0.05)(640) * 16.0),
    }

def reference(A_x, A_wqkv, A_wo, B_x, B_w1, B_b1, B_w2, B_b2, gate_w):
    def _A_ref(x, wqkv, wo):
        B, S, D = x.shape
        H = 32
        Dh = D // H
        qkv = (lambda x, *d: x.permute(*d))((x @ wqkv).reshape(B, S, 3, H, Dh), 2, 0, 3, 1, 4)
        q, k, v = qkv[0], qkv[1], qkv[2]
        scores = torch.einsum("bhqd,bhkd->bhqk", q, k) * (Dh ** -0.5)
        p = _softmax(scores, axis=-1)
        o = torch.einsum("bhqk,bhkd->bhqd", p, v)
        return (lambda x, *d: x.permute(*d))(o, 0, 2, 1, 3).reshape(B, S, D) @ wo

    def _B_ref(x, w1, b1, w2, b2):
        h = torch.einsum("bsd,df->bsf", x, w1) + b1
        zero = torch.zeros_like(h)
        r = torch.where(h > zero, h, zero)
        h = r * r
        out = torch.einsum("bsf,fd->bsd", h, w2) + b2
        return out

    x = A_x
    g = _sigmoid((x * gate_w).sum(-1, keepdims=True))
    a = _A_ref(x, A_wqkv, A_wo)
    b = _B_ref(x, B_w1, B_b1, B_w2, B_b2)
    return g * a + (1 - g) * b
```

```cpp
#include <cuda_runtime.h>
#include <cuda_bf16.h>
#include <cuda.h>
#include <stdint.h>

constexpr int SEQ = 2048, DM = 640, FF = 1728;
constexpr uint32_t POLYMASK = 0x7575u;

__device__ uint4 g_q[16 * 80 * 128];
__device__ uint4 g_kv[16 * 16 * 11 * 128];
__device__ float g_kn[96 * 32];
__device__ uint4 g_h[16 * 216 * 128];
__device__ uint4 g_o[16 * 80 * 128];
__device__ uint4 g_wp[8 * 37 * 10 * 64];
__device__ float g_gate[SEQ];
__device__ unsigned int g_done;
__device__ unsigned int g_cnt_qkv;
__device__ unsigned int g_cnt_o[16];
__device__ unsigned int g_cnt_o2[16 * 8];


__device__ __forceinline__ uint32_t smem_u32(const void* p) { uint32_t a = (uint32_t)__cvta_generic_to_shared(p); asm volatile("" : "+r"(a)); return __shfl_sync(~0u, a, 0); }
__device__ __forceinline__ uint32_t uni(uint32_t a) { asm volatile("" : "+r"(a)); return __shfl_sync(~0u, a, 0); }
__device__ __forceinline__ void mbar_init(uint32_t a, int cnt) { asm volatile("mbarrier.init.shared::cta.b64 [%0], %1;" :: "r"(a), "r"(cnt)); }
__device__ __forceinline__ void mbar_arrive(uint32_t a) { asm volatile("mbarrier.arrive.shared::cta.b64 _, [%0];" :: "r"(a) : "memory"); }
__device__ __forceinline__ void mbar_wait(uint32_t a, uint32_t parity) {
    asm volatile("{\n.reg .pred p;\n.reg .u32 n;\nmov.u32 n, 0;\n"
        "WAIT_LOOP:\n"
        "mbarrier.try_wait.parity.shared::cta.b64 p, [%0], %1, 20000;\n"
        "@p bra WAIT_DONE;\n"
        "add.u32 n, n, 1;\n"
        "setp.lt.u32 p, n, 200000;\n"
        "@p bra WAIT_LOOP;\n"
        "trap;\n"
        "WAIT_DONE:\n}" :: "r"(a), "r"(parity) : "memory");
}
__device__ __forceinline__ void mbar_spin(uint32_t a, uint32_t parity) {
    asm volatile("{\n.reg .pred p;\n.reg .u32 n;\nmov.u32 n, 0;\n"
        "WAIT_LOOP:\n"
        "mbarrier.try_wait.parity.shared::cta.b64 p, [%0], %1;\n"
        "@p bra WAIT_DONE;\n"
        "add.u32 n, n, 1;\n"
        "setp.lt.u32 p, n, 40000000;\n"
        "@p bra WAIT_LOOP;\n"
        "trap;\n"
        "WAIT_DONE:\n}" :: "r"(a), "r"(parity) : "memory");
}
__device__ __forceinline__ void mbar_expect_e(uint32_t a, uint32_t bytes) {
    asm volatile("{\n.reg .pred p;\nelect.sync _|p, 0xffffffff;\n@p mbarrier.arrive.expect_tx.shared::cta.b64 _, [%0], %1;\n}" :: "r"(a), "r"(bytes) : "memory");
}
__device__ __forceinline__ void bulk_g2s(uint32_t dst, const void* src, uint32_t bytes, uint32_t mbar) {
    asm volatile("{\n.reg .pred p;\nelect.sync _|p, 0xffffffff;\n@p cp.async.bulk.shared::cluster.global.mbarrier::complete_tx::bytes [%0], [%1], %2, [%3];\n}" :: "r"(dst), "l"(src), "r"(bytes), "r"(mbar) : "memory");
}
__device__ __forceinline__ void tma_2d(uint32_t dst, const CUtensorMap* tm, int c0, int c1, uint32_t mbar) {
    asm volatile("{\n.reg .pred p;\nelect.sync _|p, 0xffffffff;\n@p cp.async.bulk.tensor.2d.shared::cluster.global.mbarrier::complete_tx::bytes [%0], [%1, {%3, %4}], [%2];\n}"
        :: "r"(dst), "l"(tm), "r"(mbar), "r"(c0), "r"(c1) : "memory");
}
__device__ __forceinline__ void bulk_s2g(void* dst, uint32_t src, uint32_t bytes) {
    asm volatile("{\n.reg .pred p;\nelect.sync _|p, 0xffffffff;\n@p cp.async.bulk.global.shared::cta.bulk_group [%0], [%1], %2;\n}" :: "l"(dst), "r"(src), "r"(bytes) : "memory");
}
__device__ __forceinline__ void stsm4(uint32_t addr, uint32_t r0, uint32_t r1, uint32_t r2, uint32_t r3) {
    asm volatile("stmatrix.sync.aligned.m8n8.x4.shared.b16 [%0], {%1, %2, %3, %4};" :: "r"(addr), "r"(r0), "r"(r1), "r"(r2), "r"(r3) : "memory");
}
__device__ __forceinline__ void fence_async_smem() { asm volatile("fence.proxy.async.shared::cta;" ::: "memory"); }
__device__ __forceinline__ void red_release_e(unsigned int* p) {
    asm volatile("{\n.reg .pred p;\nelect.sync _|p, 0xffffffff;\n@p red.release.gpu.global.add.u32 [%0], 1;\n}" :: "l"(p) : "memory");
}
__device__ __forceinline__ void mbar_arrive_e(uint32_t a) {
    asm volatile("{\n.reg .pred p;\nelect.sync _|p, 0xffffffff;\n@p mbarrier.arrive.shared::cta.b64 _, [%0];\n}" :: "r"(a) : "memory");
}
__device__ __forceinline__ void wait_count(const unsigned int* p, uint32_t target) {
    asm volatile("{\n.reg .pred p;\n.reg .u32 n, v;\nmov.u32 n, 0;\n"
        "WAIT_LOOP:\n"
        "ld.acquire.gpu.global.u32 v, [%0];\n"
        "sub.u32 v, v, %1;\n"
        "setp.ge.s32 p, v, 0;\n"
        "@p bra WAIT_DONE;\n"
        "nanosleep.u32 200;\n"
        "add.u32 n, n, 1;\n"
        "setp.lt.u32 p, n, 8000000;\n"
        "@p bra WAIT_LOOP;\n"
        "trap;\n"
        "WAIT_DONE:\n"
        "fence.proxy.async.global;\n}" :: "l"(p), "r"(target) : "memory");
}
__device__ __forceinline__ void prefetch_tmap(const CUtensorMap* tm) { asm volatile("prefetch.tensormap [%0];" :: "l"(tm) : "memory"); }
__device__ __forceinline__ void wg_fence() { asm volatile("wgmma.fence.sync.aligned;" ::: "memory"); }
__device__ __forceinline__ void wg_commit() { asm volatile("wgmma.commit_group.sync.aligned;" ::: "memory"); }
template<int N> __device__ __forceinline__ void wg_wait() { asm volatile("wgmma.wait_group.sync.aligned %0;" :: "n"(N) : "memory"); }
__device__ __forceinline__ void pdl_wait() { asm volatile("griddepcontrol.wait;" ::: "memory"); }
__device__ __forceinline__ void pdl_launch() { asm volatile("griddepcontrol.launch_dependents;" ::: "memory"); }
__device__ __forceinline__ float ex2(float x) { float y; asm("ex2.approx.ftz.f32 %0, %1;" : "=f"(y) : "f"(x)); return y; }
__device__ __forceinline__ float sqrt_fast(float x) { float y; asm("sqrt.approx.ftz.f32 %0, %1;" : "=f"(y) : "f"(x)); return y; }
__device__ __forceinline__ uint32_t pack_bf16(float lo, float hi) { uint32_t r; asm("cvt.rn.bf16x2.f32 %0, %1, %2;" : "=r"(r) : "f"(hi), "f"(lo)); return r; }
__device__ __forceinline__ float bf_lo(uint32_t v) { return __uint_as_float(v << 16); }
__device__ __forceinline__ float bf_hi(uint32_t v) { return __uint_as_float(v & 0xffff0000u); }
template<int N> __device__ __forceinline__ void fence_regs(float (&r)[N]) {
#pragma unroll
    for (int i = 0; i < N; i++) asm volatile("" : "+f"(r[i]) :: "memory");
}
template<int N> __device__ __forceinline__ void fence_regs(uint32_t (&r)[N]) {
#pragma unroll
    for (int i = 0; i < N; i++) asm volatile("" : "+r"(r[i]) :: "memory");
}


template<uint32_t BHI, int SCALE_D> __device__ __forceinline__ void wgmma_rs_n24_tb1(float (&d)[12], uint32_t a0, uint32_t a1, uint32_t a2, uint32_t a3, uint32_t blo) {
  asm volatile("{\n.reg .pred p;\n.reg .b64 db;\nsetp.ne.b32 p, %18, 0;\nmov.b64 db, {%16, %17};\n"
  "wgmma.mma_async.sync.aligned.m64n24k16.f32.bf16.bf16 {%0, %1, %2, %3, %4, %5, %6, %7, %8, %9, %10, %11}, {%12,%13,%14,%15}, db, p, 1, 1, 1;\n}\n"
  : "+f"(d[0]), "+f"(d[1]), "+f"(d[2]), "+f"(d[3]), "+f"(d[4]), "+f"(d[5]), "+f"(d[6]), "+f"(d[7]), "+f"(d[8]), "+f"(d[9]), "+f"(d[10]), "+f"(d[11])
  : "r"(a0), "r"(a1), "r"(a2), "r"(a3), "r"(blo), "n"(BHI), "n"(SCALE_D));
}
template<uint32_t BHI, int SCALE_D> __device__ __forceinline__ void wgmma_rs_n64_tb0(float (&d)[32], uint32_t a0, uint32_t a1, uint32_t a2, uint32_t a3, uint32_t blo) {
  asm volatile("{\n.reg .pred p;\n.reg .b64 db;\nsetp.ne.b32 p, %38, 0;\nmov.b64 db, {%36, %37};\n"
  "wgmma.mma_async.sync.aligned.m64n64k16.f32.bf16.bf16 {%0, %1, %2, %3, %4, %5, %6, %7, %8, %9, %10, %11, %12, %13, %14, %15, %16, %17, %18, %19, %20, %21, %22, %23, %24, %25, %26, %27, %28, %29, %30, %31}, {%32,%33,%34,%35}, db, p, 1, 1, 0;\n}\n"
  : "+f"(d[0]), "+f"(d[1]), "+f"(d[2]), "+f"(d[3]), "+f"(d[4]), "+f"(d[5]), "+f"(d[6]), "+f"(d[7]), "+f"(d[8]), "+f"(d[9]), "+f"(d[10]), "+f"(d[11]), "+f"(d[12]), "+f"(d[13]), "+f"(d[14]), "+f"(d[15]), "+f"(d[16]), "+f"(d[17]), "+f"(d[18]), "+f"(d[19]), "+f"(d[20]), "+f"(d[21]), "+f"(d[22]), "+f"(d[23]), "+f"(d[24]), "+f"(d[25]), "+f"(d[26]), "+f"(d[27]), "+f"(d[28]), "+f"(d[29]), "+f"(d[30]), "+f"(d[31])
  : "r"(a0), "r"(a1), "r"(a2), "r"(a3), "r"(blo), "n"(BHI), "n"(SCALE_D));
}
template<uint32_t AHI, uint32_t BHI> __device__ __forceinline__ void wgmma_ss_n192_tb1(float (&d)[96], uint32_t alo, uint32_t blo, int scale_d) {
  asm volatile("{\n.reg .pred p;\n.reg .b64 da, db;\nsetp.ne.b32 p, %100, 0;\nmov.b64 da, {%96, %97};\nmov.b64 db, {%98, %99};\n"
  "wgmma.mma_async.sync.aligned.m64n192k16.f32.bf16.bf16 {%0, %1, %2, %3, %4, %5, %6, %7, %8, %9, %10, %11, %12, %13, %14, %15, %16, %17, %18, %19, %20, %21, %22, %23, %24, %25, %26, %27, %28, %29, %30, %31, %32, %33, %34, %35, %36, %37, %38, %39, %40, %41, %42, %43, %44, %45, %46, %47, %48, %49, %50, %51, %52, %53, %54, %55, %56, %57, %58, %59, %60, %61, %62, %63, %64, %65, %66, %67, %68, %69, %70, %71, %72, %73, %74, %75, %76, %77, %78, %79, %80, %81, %82, %83, %84, %85, %86, %87, %88, %89, %90, %91, %92, %93, %94, %95}, da, db, p, 1, 1, 0, 1;\n}\n"
  : "+f"(d[0]), "+f"(d[1]), "+f"(d[2]), "+f"(d[3]), "+f"(d[4]), "+f"(d[5]), "+f"(d[6]), "+f"(d[7]), "+f"(d[8]), "+f"(d[9]), "+f"(d[10]), "+f"(d[11]), "+f"(d[12]), "+f"(d[13]), "+f"(d[14]), "+f"(d[15]), "+f"(d[16]), "+f"(d[17]), "+f"(d[18]), "+f"(d[19]), "+f"(d[20]), "+f"(d[21]), "+f"(d[22]), "+f"(d[23]), "+f"(d[24]), "+f"(d[25]), "+f"(d[26]), "+f"(d[27]), "+f"(d[28]), "+f"(d[29]), "+f"(d[30]), "+f"(d[31]), "+f"(d[32]), "+f"(d[33]), "+f"(d[34]), "+f"(d[35]), "+f"(d[36]), "+f"(d[37]), "+f"(d[38]), "+f"(d[39]), "+f"(d[40]), "+f"(d[41]), "+f"(d[42]), "+f"(d[43]), "+f"(d[44]), "+f"(d[45]), "+f"(d[46]), "+f"(d[47]), "+f"(d[48]), "+f"(d[49]), "+f"(d[50]), "+f"(d[51]), "+f"(d[52]), "+f"(d[53]), "+f"(d[54]), "+f"(d[55]), "+f"(d[56]), "+f"(d[57]), "+f"(d[58]), "+f"(d[59]), "+f"(d[60]), "+f"(d[61]), "+f"(d[62]), "+f"(d[63]), "+f"(d[64]), "+f"(d[65]), "+f"(d[66]), "+f"(d[67]), "+f"(d[68]), "+f"(d[69]), "+f"(d[70]), "+f"(d[71]), "+f"(d[72]), "+f"(d[73]), "+f"(d[74]), "+f"(d[75]), "+f"(d[76]), "+f"(d[77]), "+f"(d[78]), "+f"(d[79]), "+f"(d[80]), "+f"(d[81]), "+f"(d[82]), "+f"(d[83]), "+f"(d[84]), "+f"(d[85]), "+f"(d[86]), "+f"(d[87]), "+f"(d[88]), "+f"(d[89]), "+f"(d[90]), "+f"(d[91]), "+f"(d[92]), "+f"(d[93]), "+f"(d[94]), "+f"(d[95])
  : "r"(alo), "n"(AHI), "r"(blo), "n"(BHI), "r"(scale_d));
}
template<uint32_t AHI, uint32_t BHI> __device__ __forceinline__ void wgmma_ss_n256_tb1(float (&d)[128], uint32_t alo, uint32_t blo, int scale_d) {
  asm volatile("{\n.reg .pred p;\n.reg .b64 da, db;\nsetp.ne.b32 p, %132, 0;\nmov.b64 da, {%128, %129};\nmov.b64 db, {%130, %131};\n"
  "wgmma.mma_async.sync.aligned.m64n256k16.f32.bf16.bf16 {%0, %1, %2, %3, %4, %5, %6, %7, %8, %9, %10, %11, %12, %13, %14, %15, %16, %17, %18, %19, %20, %21, %22, %23, %24, %25, %26, %27, %28, %29, %30, %31, %32, %33, %34, %35, %36, %37, %38, %39, %40, %41, %42, %43, %44, %45, %46, %47, %48, %49, %50, %51, %52, %53, %54, %55, %56, %57, %58, %59, %60, %61, %62, %63, %64, %65, %66, %67, %68, %69, %70, %71, %72, %73, %74, %75, %76, %77, %78, %79, %80, %81, %82, %83, %84, %85, %86, %87, %88, %89, %90, %91, %92, %93, %94, %95, %96, %97, %98, %99, %100, %101, %102, %103, %104, %105, %106, %107, %108, %109, %110, %111, %112, %113, %114, %115, %116, %117, %118, %119, %120, %121, %122, %123, %124, %125, %126, %127}, da, db, p, 1, 1, 0, 1;\n}\n"
  : "+f"(d[0]), "+f"(d[1]), "+f"(d[2]), "+f"(d[3]), "+f"(d[4]), "+f"(d[5]), "+f"(d[6]), "+f"(d[7]), "+f"(d[8]), "+f"(d[9]), "+f"(d[10]), "+f"(d[11]), "+f"(d[12]), "+f"(d[13]), "+f"(d[14]), "+f"(d[15]), "+f"(d[16]), "+f"(d[17]), "+f"(d[18]), "+f"(d[19]), "+f"(d[20]), "+f"(d[21]), "+f"(d[22]), "+f"(d[23]), "+f"(d[24]), "+f"(d[25]), "+f"(d[26]), "+f"(d[27]), "+f"(d[28]), "+f"(d[29]), "+f"(d[30]), "+f"(d[31]), "+f"(d[32]), "+f"(d[33]), "+f"(d[34]), "+f"(d[35]), "+f"(d[36]), "+f"(d[37]), "+f"(d[38]), "+f"(d[39]), "+f"(d[40]), "+f"(d[41]), "+f"(d[42]), "+f"(d[43]), "+f"(d[44]), "+f"(d[45]), "+f"(d[46]), "+f"(d[47]), "+f"(d[48]), "+f"(d[49]), "+f"(d[50]), "+f"(d[51]), "+f"(d[52]), "+f"(d[53]), "+f"(d[54]), "+f"(d[55]), "+f"(d[56]), "+f"(d[57]), "+f"(d[58]), "+f"(d[59]), "+f"(d[60]), "+f"(d[61]), "+f"(d[62]), "+f"(d[63]), "+f"(d[64]), "+f"(d[65]), "+f"(d[66]), "+f"(d[67]), "+f"(d[68]), "+f"(d[69]), "+f"(d[70]), "+f"(d[71]), "+f"(d[72]), "+f"(d[73]), "+f"(d[74]), "+f"(d[75]), "+f"(d[76]), "+f"(d[77]), "+f"(d[78]), "+f"(d[79]), "+f"(d[80]), "+f"(d[81]), "+f"(d[82]), "+f"(d[83]), "+f"(d[84]), "+f"(d[85]), "+f"(d[86]), "+f"(d[87]), "+f"(d[88]), "+f"(d[89]), "+f"(d[90]), "+f"(d[91]), "+f"(d[92]), "+f"(d[93]), "+f"(d[94]), "+f"(d[95]), "+f"(d[96]), "+f"(d[97]), "+f"(d[98]), "+f"(d[99]), "+f"(d[100]), "+f"(d[101]), "+f"(d[102]), "+f"(d[103]), "+f"(d[104]), "+f"(d[105]), "+f"(d[106]), "+f"(d[107]), "+f"(d[108]), "+f"(d[109]), "+f"(d[110]), "+f"(d[111]), "+f"(d[112]), "+f"(d[113]), "+f"(d[114]), "+f"(d[115]), "+f"(d[116]), "+f"(d[117]), "+f"(d[118]), "+f"(d[119]), "+f"(d[120]), "+f"(d[121]), "+f"(d[122]), "+f"(d[123]), "+f"(d[124]), "+f"(d[125]), "+f"(d[126]), "+f"(d[127])
  : "r"(alo), "n"(AHI), "r"(blo), "n"(BHI), "r"(scale_d));
}
template<uint32_t AHI, uint32_t BHI> __device__ __forceinline__ void wgmma_ss_n64_tb1(float (&d)[32], uint32_t alo, uint32_t blo, int scale_d) {
  asm volatile("{\n.reg .pred p;\n.reg .b64 da, db;\nsetp.ne.b32 p, %36, 0;\nmov.b64 da, {%32, %33};\nmov.b64 db, {%34, %35};\n"
  "wgmma.mma_async.sync.aligned.m64n64k16.f32.bf16.bf16 {%0, %1, %2, %3, %4, %5, %6, %7, %8, %9, %10, %11, %12, %13, %14, %15, %16, %17, %18, %19, %20, %21, %22, %23, %24, %25, %26, %27, %28, %29, %30, %31}, da, db, p, 1, 1, 0, 1;\n}\n"
  : "+f"(d[0]), "+f"(d[1]), "+f"(d[2]), "+f"(d[3]), "+f"(d[4]), "+f"(d[5]), "+f"(d[6]), "+f"(d[7]), "+f"(d[8]), "+f"(d[9]), "+f"(d[10]), "+f"(d[11]), "+f"(d[12]), "+f"(d[13]), "+f"(d[14]), "+f"(d[15]), "+f"(d[16]), "+f"(d[17]), "+f"(d[18]), "+f"(d[19]), "+f"(d[20]), "+f"(d[21]), "+f"(d[22]), "+f"(d[23]), "+f"(d[24]), "+f"(d[25]), "+f"(d[26]), "+f"(d[27]), "+f"(d[28]), "+f"(d[29]), "+f"(d[30]), "+f"(d[31])
  : "r"(alo), "n"(AHI), "r"(blo), "n"(BHI), "r"(scale_d));
}


constexpr uint32_t DHI_SW128 = (1024u >> 4) | (1u << 30);
constexpr uint32_t DHI_SW64 = (512u >> 4) | (2u << 30);

__device__ __forceinline__ float quad_sum(float v) {
    v += __shfl_xor_sync(~0u, v, 1);
    v += __shfl_xor_sync(~0u, v, 2);
    return v;
}
__device__ __forceinline__ float sq2(uint32_t v) { float l = bf_lo(v), h = bf_hi(v); return l * l + h * h; }

constexpr int K1_STAGES = 6;
constexpr int K1_A_BYTES = 128 * 32 * 2, K1_B_BYTES = 4 * 64 * 32 * 2, K1_STAGE = K1_A_BYTES + K1_B_BYTES;
constexpr int K1_SMEM = K1_STAGES * K1_STAGE + 4 * 16384 + 1024;


__device__ __forceinline__ void k1_cvt(const float* a, uint32_t (&v)[16], int u, const float2* bp) {
    if (u >= 30) {
#pragma unroll
        for (int j = 0; j < 8; j++) {
            const float2 bb = bp[j * 4];
            uint32_t r0, r1;
            asm("cvt.rn.relu.bf16x2.f32 %0, %1, %2;" : "=r"(r0) : "f"(a[4 * j + 1] + bb.y), "f"(a[4 * j] + bb.x));
            asm("cvt.rn.relu.bf16x2.f32 %0, %1, %2;" : "=r"(r1) : "f"(a[4 * j + 3] + bb.y), "f"(a[4 * j + 2] + bb.x));
            asm("mul.rn.bf16x2 %0, %1, %1;" : "=r"(v[2 * j]) : "r"(r0));
            asm("mul.rn.bf16x2 %0, %1, %1;" : "=r"(v[2 * j + 1]) : "r"(r1));
        }
    } else {
        const float qs = u < 10 ? 0.22360679774997896f * 1.4426950408889634f : 1.f;
#pragma unroll
        for (int j = 0; j < 8; j++) {
            v[2 * j] = pack_bf16(a[4 * j] * qs, a[4 * j + 1] * qs);
            v[2 * j + 1] = pack_bf16(a[4 * j + 2] * qs, a[4 * j + 3] * qs);
        }
    }
}
__device__ __forceinline__ uint4 lds128(uint32_t a) { uint4 v; asm volatile("ld.shared.v4.u32 {%0,%1,%2,%3}, [%4];" : "=r"(v.x), "=r"(v.y), "=r"(v.z), "=r"(v.w) : "r"(a) : "memory"); return v; }

template<int NU>
__device__ __forceinline__ void k1_mainloop(float (&acc)[NU * 32], uint32_t dA, uint32_t dB, uint32_t full0, uint32_t empty0, uint32_t& st, uint32_t& ph) {
    uint32_t prev = 0;
#pragma unroll 1
    for (int kb = 0; kb < 20; kb++) {
        mbar_spin(full0 + 8 * st, ph);
        const uint32_t so = st * (K1_STAGE >> 4);
        wg_fence();
#pragma unroll
        for (int k = 0; k < 2; k++) {
            if constexpr (NU == 4) wgmma_ss_n256_tb1<DHI_SW64, DHI_SW128>(acc, dA + so + k * 2, dB + so + k * 128, (kb | k) != 0);
            if constexpr (NU == 3) wgmma_ss_n192_tb1<DHI_SW64, DHI_SW128>(acc, dA + so + k * 2, dB + so + k * 128, (kb | k) != 0);
            if constexpr (NU == 1) wgmma_ss_n64_tb1<DHI_SW64, DHI_SW128>(acc, dA + so + k * 2, dB + so + k * 128, (kb | k) != 0);
        }
        wg_commit();
        wg_wait<1>();
        if (kb > 0) mbar_arrive_e(empty0 + 8 * prev);
        prev = st;
        if (++st == K1_STAGES) { st = 0; ph ^= 1; }
    }
    wg_wait<0>();
    fence_regs(acc);
    mbar_arrive_e(empty0 + 8 * prev);
}

__global__ void __launch_bounds__(384, 1)
k1_gemm(const __grid_constant__ CUtensorMap tm_x, const __grid_constant__ CUtensorMap tm_wqkv, const __grid_constant__ CUtensorMap tm_w1,
        const __nv_bfloat16* __restrict__ x, const __nv_bfloat16* __restrict__ gate_w, const __nv_bfloat16* __restrict__ b1,
        const __nv_bfloat16* __restrict__ w2, const __nv_bfloat16* __restrict__ wo) {
    extern __shared__ __align__(1024) uint8_t smem_raw[];
    __shared__ __align__(8) uint64_t bars[2 * K1_STAGES + 11];
    __shared__ float2 sbias[7 * 32];
    const uint32_t sbase = (smem_u32(smem_raw) + 1023u) & ~1023u;
    const uint32_t full0 = smem_u32(bars), empty0 = full0 + 8 * K1_STAGES, sfull0 = empty0 + 8 * K1_STAGES, sempty0 = sfull0 + 40;
    const uint32_t stg0 = sbase + K1_STAGES * K1_STAGE;
    const int tid = threadIdx.x, lane = tid & 31;
    const int warp = __shfl_sync(~0u, tid >> 5, 0);
    const bool extra = blockIdx.x >= 128;
    const int c = extra ? (blockIdx.x - 128) * 4 : (blockIdx.x & 15), r = blockIdx.x >> 4;
    if (tid == 256) {
        prefetch_tmap(&tm_x); prefetch_tmap(&tm_wqkv); prefetch_tmap(&tm_w1);
        for (int i = 0; i < K1_STAGES; i++) { mbar_init(full0 + 8 * i, 1); mbar_init(empty0 + 8 * i, 8); }
        for (int i = 0; i < 5; i++) mbar_init(sfull0 + 8 * i, 8);
        mbar_init(sempty0, 3);
        mbar_init(sempty0 + 32, 32);
        mbar_init(sempty0 + 40, 2);
        asm volatile("fence.mbarrier_init.release.cluster;" ::: "memory");
    }
    if (warp == 8) asm volatile("bar.arrive 1, 384;" ::: "memory");
    else asm volatile("bar.sync 1, 384;" ::: "memory");
    if (warp == 8) {
        __syncwarp();
        uint32_t st = 0, ph = 1;
        const int npass = extra ? 4 : 2;
#pragma unroll 1
        for (int p = 0; p < npass; p++) {
            const int nu = extra ? 1 : 4 - p, u0 = extra ? 56 : r + p * 32, row = (extra ? c + p : c) * 128;
            const CUtensorMap* tw[4]; int col[4];
#pragma unroll
            for (int j = 0; j < 4; j++) { const int u = u0 + j * 8; tw[j] = u < 30 ? &tm_wqkv : &tm_w1; col[j] = (u < 30 ? u : u - 30) * 64; }
#pragma unroll 1
            for (int kb = 0; kb < 640; kb += 32) {
                mbar_spin(empty0 + 8 * st, ph);
                const uint32_t sa = sbase + st * K1_STAGE, fb = full0 + 8 * st;
                mbar_expect_e(fb, K1_A_BYTES + nu * 4096);
                tma_2d(sa, &tm_x, kb, row, fb);
#pragma unroll
                for (int j = 0; j < 4; j++) if (j < nu) tma_2d(sa + K1_A_BYTES + j * 4096, tw[j], col[j], kb, fb);
                if (++st == K1_STAGES) { st = 0; ph ^= 1; }
                if (p == npass - 1 && kb == 384) pdl_launch();
            }
        }
        return;
    }
    if (warp == 9) {
#pragma unroll
        for (int n = 0; n < 7; n++) {
            const int u = extra ? 56 : r + n * 8;
            if (u >= 30) { const uint32_t bb = __ldg((const uint32_t*)(b1 + (u - 30) * 64) + lane); sbias[n * 32 + lane] = make_float2(bf_lo(bb), bf_hi(bb)); }
        }
        mbar_arrive(sempty0 + 32);
        if (blockIdx.x < 120) {
            const int wk = (blockIdx.x / 20) * 8 + (lane & 7), wch = (blockIdx.x % 20) * 4 + (lane >> 3);
            uint4* wd = g_wp + ((wch / 10) * 370 + 270 + wch % 10) * 64;
            uint4 wv[14];
#pragma unroll
            for (int u = 0; u < 14; u++) {
                const int k = wk + u * 48, kp = k >= 320, kh = (k - kp * 320) / 20;
                if (k < 640) wv[u] = __ldg((const uint4*)(wo + (size_t)(k - kp * 300 + kh * 20) * DM) + wch);
            }
#pragma unroll
            for (int u = 0; u < 14; u++) { const int k = wk + u * 48; if (k < 640) wd[(k >> 6) * 640 + (k & 63)] = wv[u]; }
        }
        if (!extra) {
        uint64_t dl;
        {
            const int u = r + (lane & ~7), g = (u >= 20 ? u - 20 : u - 10) * 8 + (lane & 7), hp = g / 5, bb = g - hp * 5;
            const uint4* d = u < 10 ? g_q + ((size_t)c * 80 + u * 8 + (lane & 7)) * 128
                           : u >= 30 ? g_h + ((size_t)c * 216 + (u - 30) * 8 + (lane & 7)) * 128
                           : g_kv + ((size_t)(hp * 16 + c) * 11 + (u < 20 ? 3 + bb : (bb < 3 ? bb : bb + 5))) * 128;
            dl = (u >= 20 && u < 30 && bb == 2) ? 0ull : (uint64_t)d;
        }
            mbar_wait(sfull0, 0);
#pragma unroll 1
            for (int j = 0; j < 32; j += 2) {
                const uint64_t dj = __shfl_sync(~0u, dl, j + (lane & 1));
                if (lane < 2 && dj)
                    asm volatile("cp.async.bulk.global.shared::cta.bulk_group [%0], [%1], %2;" :: "l"(dj), "r"(stg0 + (j + lane) * 2048), "r"(2048) : "memory");
                asm volatile("cp.async.bulk.commit_group;\ncp.async.bulk.wait_group.read 0;" ::: "memory");
                __syncwarp();
            }
            mbar_arrive_e(sempty0);
            asm volatile("cp.async.bulk.wait_group 0;" ::: "memory");
            asm volatile("fence.proxy.async.global;" ::: "memory");
            mbar_wait(sempty0 + 40, 0);
            __syncwarp();
            red_release_e(&g_cnt_qkv);
        }
#pragma unroll 1
        for (int n = 0; n < (extra ? 4 : 3); n++) {
            mbar_wait(sfull0 + 8 * (n + 1), 0);
            bulk_s2g(g_h + ((size_t)(extra ? c + n : c) * 216 + (extra ? 26 : r + 2 + n * 8) * 8) * 128, stg0 + n * 16384, 16384);
            asm volatile("cp.async.bulk.commit_group;" ::: "memory");
        }
        asm volatile("cp.async.bulk.wait_group.read 0;" ::: "memory");
        return;
    }
    if (warp >= 10) {
        if (extra) return;
        const int wi = blockIdx.x * 2 + (warp - 10), wk = (wi / 20) * 8 + (lane & 7), wch = (wi % 20) * 4 + (lane >> 3);
        uint4 wv[18];
        if (wi < 240) {
#pragma unroll
            for (int u = 0; u < 18; u++) wv[u] = __ldg((const uint4*)(w2 + (size_t)(wk + u * 96) * DM) + wch);
        }
        {
            uint32_t gw[10];
#pragma unroll
            for (int j = 0; j < 10; j++) gw[j] = ((const uint32_t*)gate_w)[j * 32 + lane];
#pragma unroll 4
            for (int i = 0; i < 8; i++) {
                const int row = c * 128 + r * 16 + (warp - 10) * 8 + i;
                const uint32_t* xr = (const uint32_t*)(x + (size_t)row * DM);
                float s = 0.f;
#pragma unroll
                for (int j = 0; j < 10; j++) { uint32_t v = xr[j * 32 + lane]; s += bf_lo(v) * bf_lo(gw[j]) + bf_hi(v) * bf_hi(gw[j]); }
#pragma unroll
                for (int o = 16; o; o >>= 1) s += __shfl_xor_sync(~0u, s, o);
                if (lane == 0) g_gate[row] = 1.f / (1.f + __expf(-s));
            }
        }
        if (wi < 240) {
            uint4* wd = g_wp + ((wch / 10) * 370 + wch % 10) * 64;
#pragma unroll
            for (int u = 0; u < 18; u++) { const int k = wk + u * 96; wd[(k >> 6) * 640 + (k & 63)] = wv[u]; }
        }
        mbar_wait(sfull0, 0);
#pragma unroll 1
        for (int n = 1; n < 4; n++) {
            const int uq = r + n * 8;
            if (uq < 10 || uq >= 30) continue;
            const uint32_t sb = stg0 + n * 16384 + (warp - 10) * 1024;
            if (uq < 20) {
                const int gq = (uq - 10) * 8 + (lane >> 2), hq = gq / 5, bq = gq - hq * 5;
                uint32_t m0 = 0, m1 = 0;
#pragma unroll
                for (int i = 0; i < 16; i++) {
                    const uint4 w = lds128(sb + (lane >> 2) * 2048 + ((((i + (lane >> 2)) & 15) * 4 + (lane & 3)) * 16));
                    uint32_t a, b2, lohi;
                    asm("mul.rn.bf16x2 %0, %1, %1;" : "=r"(a) : "r"(w.x));
                    asm("mul.rn.bf16x2 %0, %1, %1;" : "=r"(b2) : "r"(w.z));
                    asm("fma.rn.bf16x2 %0, %1, %1, %0;" : "+r"(a) : "r"(w.y));
                    asm("fma.rn.bf16x2 %0, %1, %1, %0;" : "+r"(b2) : "r"(w.w));
                    asm("add.rn.bf16x2 %0, %1, %2;" : "=r"(lohi) : "r"(__byte_perm(a, b2, 0x5410)), "r"(__byte_perm(a, b2, 0x7632)));
                    const float lo = bf_lo(lohi), hi = bf_hi(lohi);
                    m0 = max(m0, __float_as_uint(bq == 2 ? lo : lo + hi));
                    m1 = max(m1, __float_as_uint(hi));
                }
                m0 = max(m0, __shfl_xor_sync(~0u, m0, 1)); m1 = max(m1, __shfl_xor_sync(~0u, m1, 1));
                m0 = max(m0, __shfl_xor_sync(~0u, m0, 2)); m1 = max(m1, __shfl_xor_sync(~0u, m1, 2));
                float* kn = g_kn + c * 2 + (warp - 10);
                if ((lane & 3) == 0) kn[(hq * 6 + bq + (bq > 2)) * 32] = __uint_as_float(m0);
                if ((lane & 3) == 1 && bq == 2) kn[(hq * 6 + 3) * 32] = __uint_as_float(m1);
            } else {
                const int g0 = (uq - 20) * 8, j0 = (7 - g0 % 5) % 5;
#pragma unroll
                for (int j = j0; j < 8; j += 5) {
                    uint4* d = g_kv + ((size_t)(((g0 + j) / 5) * 16 + c) * 11 + 2) * 128 + (warp - 10) * 64 + lane;
#pragma unroll
                    for (int i = 0; i < 2; i++) {
                        const uint4 w = lds128(sb + j * 2048 + (i * 32 + lane) * 16);
                        d[i * 32] = make_uint4(w.x, w.y, 0x3F80u, 0u);
                        d[i * 32 + 8 * 128] = make_uint4(0x3F80u, 0u, w.z, w.w);
                    }
                }
            }
        }
        __syncwarp();
        mbar_arrive_e(sempty0);
        mbar_arrive_e(sempty0 + 40);
        return;
    }
    const int wg = warp >> 2;
    const uint32_t dA = uni((((sbase + wg * 4096) & 0x3FFFF) >> 4) | (1u << 16));
    const uint32_t dB = uni((((sbase + K1_A_BYTES) & 0x3FFFF) >> 4) | ((4096u >> 4) << 16));
    float acc[128];
    const int npass = extra ? 4 : 2;
    uint32_t st = 0, ph = 0;
#pragma unroll 1
    for (int p = 0; p < npass; p++) {
        if (extra) k1_mainloop<1>(reinterpret_cast<float (&)[32]>(acc), dA, dB, full0, empty0, st, ph);
        else if (p == 0) k1_mainloop<4>(acc, dA, dB, full0, empty0, st, ph);
        else k1_mainloop<3>(reinterpret_cast<float (&)[96]>(acc), dA, dB, full0, empty0, st, ph);
        if (p == 0) mbar_spin(sempty0 + 32, 0);
        if (!extra && p == 1) mbar_spin(sempty0, 0);
        const uint32_t sa = stg0 + (lane >> 4) * 2048 + (warp * 16 + (lane & 15)) * 16;
        const float2* bp = sbias + (lane & 3);
        auto put = [&](const uint32_t (&v)[16], int buf) {
#pragma unroll
            for (int i = 0; i < 4; i++) stsm4(sa + buf * 16384 + i * 4096, v[4 * i], v[4 * i + 1], v[4 * i + 2], v[4 * i + 3]);
        };
        auto hand = [&](int buf) { fence_async_smem(); __syncwarp(); mbar_arrive_e(sfull0 + 8 + 8 * buf); };
        uint32_t v[16];
        if (!extra && p == 0) {
            k1_cvt(acc, v, 0, bp); put(v, 0);
            k1_cvt(acc + 32, v, r < 2 ? 0 : 10, bp); put(v, 1);
            k1_cvt(acc + 64, v, 10, bp); put(v, 2);
            k1_cvt(acc + 96, v, r < 6 ? 10 : 30, bp + 96); put(v, 3);
            fence_async_smem();
            __syncwarp();
            mbar_arrive_e(sfull0);
        } else {
            const int b0 = extra ? p : 0;
            k1_cvt(acc, v, 30, bp + 128); put(v, b0); hand(b0);
            if (!extra) {
                k1_cvt(acc + 32, v, 30, bp + 160); put(v, 1); hand(1);
                k1_cvt(acc + 64, v, 30, bp + 192); put(v, 2); hand(2);
            }
        }
    }
}

constexpr int K2_STAGES = 4;
constexpr int KV_BYTES = 6 * 128 * 16;
constexpr int K2_SMEM = K2_STAGES * KV_BYTES + 2048 + 128;

__device__ __forceinline__ uint32_t ex2_pk(float lo, float hi) {
    uint32_t pk = __byte_perm(__float_as_uint(lo), __float_as_uint(hi), 0x6521);
    uint32_t m, q, r;
    asm("lop3.b32 %0, %1, %2, %3, 0xEA;" : "=r"(m) : "r"(pk), "r"(0x007F007Fu), "r"(0x3F803F80u));
    asm("fma.rn.bf16x2 %0, %1, %2, %3;" : "=r"(q) : "r"(0x3eae3eaeu), "r"(m), "r"(0xbcb9bcb9u));
    asm("fma.rn.bf16x2 %0, %1, %2, %3;" : "=r"(q) : "r"(q), "r"(m), "r"(0x3f303f30u));
    asm("lop3.b32 %0, %1, %2, %3, 0xE4;" : "=r"(r) : "r"(pk), "r"(q), "r"(0x7F807F80u));
    return r;
}

template<int SCALE_D> __device__ __forceinline__ void qk_mma(float (&d)[32], uint32_t a0, uint32_t a1, uint32_t a2, uint32_t a3, uint64_t db) {
  asm volatile("{\n.reg .pred p;\nsetp.ne.b32 p, %37, 0;\n"
  "wgmma.mma_async.sync.aligned.m64n64k16.f32.bf16.bf16 {%0, %1, %2, %3, %4, %5, %6, %7, %8, %9, %10, %11, %12, %13, %14, %15, %16, %17, %18, %19, %20, %21, %22, %23, %24, %25, %26, %27, %28, %29, %30, %31}, {%32,%33,%34,%35}, %36, p, 1, 1, 0;\n}\n"
  : "+f"(d[0]), "+f"(d[1]), "+f"(d[2]), "+f"(d[3]), "+f"(d[4]), "+f"(d[5]), "+f"(d[6]), "+f"(d[7]), "+f"(d[8]), "+f"(d[9]), "+f"(d[10]), "+f"(d[11]), "+f"(d[12]), "+f"(d[13]), "+f"(d[14]), "+f"(d[15]), "+f"(d[16]), "+f"(d[17]), "+f"(d[18]), "+f"(d[19]), "+f"(d[20]), "+f"(d[21]), "+f"(d[22]), "+f"(d[23]), "+f"(d[24]), "+f"(d[25]), "+f"(d[26]), "+f"(d[27]), "+f"(d[28]), "+f"(d[29]), "+f"(d[30]), "+f"(d[31])
  : "r"(a0), "r"(a1), "r"(a2), "r"(a3), "l"(db), "n"(SCALE_D));
}
__device__ __forceinline__ void pv_mma(float (&d)[12], uint32_t a0, uint32_t a1, uint32_t a2, uint32_t a3, uint64_t db) {
  asm volatile("{\n.reg .pred p;\nsetp.ne.b32 p, 1, 0;\n"
  "wgmma.mma_async.sync.aligned.m64n24k16.f32.bf16.bf16 {%0, %1, %2, %3, %4, %5, %6, %7, %8, %9, %10, %11}, {%12,%13,%14,%15}, %16, p, 1, 1, 1;\n}\n"
  : "+f"(d[0]), "+f"(d[1]), "+f"(d[2]), "+f"(d[3]), "+f"(d[4]), "+f"(d[5]), "+f"(d[6]), "+f"(d[7]), "+f"(d[8]), "+f"(d[9]), "+f"(d[10]), "+f"(d[11])
  : "r"(a0), "r"(a1), "r"(a2), "r"(a3), "l"(db));
}
__device__ __forceinline__ uint64_t mk64(uint32_t lo, uint32_t hi) { uint64_t v; asm volatile("mov.b64 %0, {%1, %2};" : "=l"(v) : "r"(lo), "r"(hi)); return v; }
__global__ void __maxnreg__(96) k2_attn() {
    extern __shared__ uint8_t smem_raw[];
    __shared__ __align__(8) uint64_t bars[2 * K2_STAGES + 1];
    const uint32_t sbase = (smem_u32(smem_raw) + 127u) & ~127u;
    const uint32_t full0 = smem_u32(bars), empty0 = full0 + 8 * K2_STAGES;
    const int tid = threadIdx.x, t128 = tid & 127, lane = tid & 31, tq = lane & 3;
    const int wg = __shfl_sync(~0u, tid >> 7, 0);
    const int hp = blockIdx.x & 15, qb = blockIdx.x >> 4;
    if (tid == 0) {
        for (int i = 0; i < K2_STAGES; i++) { mbar_init(full0 + 8 * i, 1); mbar_init(empty0 + 8 * i, 16); }
        mbar_init(empty0 + 8 * K2_STAGES, 16);
        asm volatile("fence.mbarrier_init.release.cluster;" ::: "memory");
    }
    if (tid < 128) {
        const uint32_t w0 = ((POLYMASK >> (tid >> 3)) & 1) ? 0x3F803F80u : 0x00003F80u;
        asm volatile("st.shared.v4.u32 [%0], {%1, %3, %2, %2};" :: "r"(sbase + K2_STAGES * KV_BYTES + tid * 16), "r"(w0), "r"(0u), "r"(w0 >> 16) : "memory");
        asm volatile("fence.proxy.async.shared::cta;" ::: "memory");
    }
    if (__shfl_sync(~0u, tid >> 5, 0) == 0) {
        uint32_t dn, cq;
        asm volatile("ld.volatile.global.u32 %0, [%2];\nld.acquire.gpu.global.u32 %1, [%3];" : "=r"(dn), "=r"(cq) : "l"(&g_done), "l"(&g_cnt_qkv) : "memory");
        const uint32_t target = uni(((dn >> 7) + 1) * 128);
        if ((int)(uni(cq) - target) < 0) wait_count(&g_cnt_qkv, target);
    }
    __syncthreads();
    const uint8_t* kvsrc = (const uint8_t*)g_kv + (size_t)hp * 16 * 11 * 2048;
    const bool loader = __shfl_sync(~0u, t128 >> 5, 0) == 0;
    const uint32_t ldsel = uni(loader ? wg : 99);
    auto first_load = [&]() {
        asm volatile("fence.proxy.async.global;" ::: "memory");
        mbar_expect_e(full0 + 8 * wg, KV_BYTES);
        bulk_g2s(sbase + wg * KV_BYTES, kvsrc + (size_t)(wg * 11) * 2048, KV_BYTES, full0 + 8 * wg);
    };
    if (ldsel == 0) first_load();
    auto refill = [&](int t) {
        const int rs = t & 3;
        mbar_spin(empty0 + 8 * rs, ((t >> 2) - (rs != 3)) & 1);
        mbar_expect_e(full0 + 8 * rs, KV_BYTES);
        bulk_g2s(sbase + rs * KV_BYTES, kvsrc + (size_t)((t & 15) * 11 + (t >> 4) * 5) * 2048, KV_BYTES, full0 + 8 * rs);
    };
    auto publish0 = [&]() {
        mbar_spin(empty0 + 8 * K2_STAGES, 0);
        asm volatile("{\n.reg .pred p;\nelect.sync _|p, 0xffffffff;\n@p fence.acq_rel.gpu;\n"
                     "@p red.relaxed.gpu.global.add.u32 [%0], 8;\n@p red.relaxed.gpu.global.add.u32 [%0+4], 8;\n}" :: "l"(g_cnt_o + qb * 2) : "memory");
    };
    auto side_jobs = [&](int t) {
        if (t >= 1 && t < 29) refill(t + 3);
        if (t == 17) publish0();
    };
    uint32_t relbar = empty0 + 24;
    if (__shfl_sync(~0u, tid >> 5, 0) == 15) { pdl_wait(); pdl_launch(); }
    const int rt = qb * 4 + wg;
    const uint32_t* qp = (const uint32_t*)g_q + ((size_t)((rt >> 1) * 80 + hp * 5) * 128 + (rt & 1) * 64 + (t128 >> 5) * 16 + (lane >> 2)) * 4 + tq;
    uint2 b0, b1, b2;
    uint32_t e0, e1, e0n, e1n, fastbits;
    {
        uint2 q[5];
#pragma unroll
        for (int i = 0; i < 5; i++) q[i] = make_uint2(__ldcg(qp + i * 512), __ldcg(qp + i * 512 + 32));
        uint32_t km[6];
#pragma unroll
        for (int i = 0; i < 6; i++) km[i] = __reduce_max_sync(~0u, __ldcg((const uint32_t*)g_kn + (hp * 6 + i) * 32 + lane));
        if (ldsel - 1 < 3) first_load();
        float bx[2], by[2];
        {
            float sx = sq2(q[2].x), sy = sq2(q[2].y);
            sx += __shfl_xor_sync(~0u, sx, 1); sy += __shfl_xor_sync(~0u, sy, 1);
            const float ox = __shfl_xor_sync(~0u, sx, 2), oy = __shfl_xor_sync(~0u, sy, 2);
            bx[0] = sqrt_fast((tq < 2 ? sx : ox) * __uint_as_float(km[2])); by[0] = sqrt_fast((tq < 2 ? sy : oy) * __uint_as_float(km[2]));
            bx[1] = sqrt_fast((tq < 2 ? ox : sx) * __uint_as_float(km[3])); by[1] = sqrt_fast((tq < 2 ? oy : sy) * __uint_as_float(km[3]));
        }
#pragma unroll
        for (int i = 0; i < 4; i++) {
            const int blk = i < 2 ? i : i + 1, ch = i < 2 ? i : i + 2;
            bx[i >> 1] += sqrt_fast(quad_sum(sq2(q[blk].x)) * __uint_as_float(km[ch]));
            by[i >> 1] += sqrt_fast(quad_sum(sq2(q[blk].y)) * __uint_as_float(km[ch]));
        }
        uint32_t f[2], ex[2], ey[2];
#pragma unroll
        for (int h = 0; h < 2; h++) {
            const float bd0 = bx[h] * 1.03f + 0.05f, bd1 = by[h] * 1.03f + 0.05f;
            const bool ok = (bd0 <= 50.f) && (bd1 <= 50.f);
            asm volatile("{\n.reg .pred p, q;\nsetp.ne.u32 p, %1, 0;\nbarrier.cta.red.and.pred.aligned q, %2, 128, p;\nselp.u32 %0, 1, 0, q;\n}"
                         : "=r"(f[h]) : "r"((uint32_t)ok), "r"(wg + 1) : "memory");
            ex[h] = !f[h] || tq > 1 ? 0u : (tq ? 0xBF80u : ((__float_as_uint(-bd0) >> 16) | (0x43C0u << 16)));
            ey[h] = !f[h] || tq > 1 ? 0u : (tq ? 0xBF80u : ((__float_as_uint(-bd1) >> 16) | (0x43C0u << 16)));
        }
        fastbits = f[0] | (f[1] << 1);
        e0 = ex[0]; e1 = ey[0]; e0n = ex[1]; e1n = ey[1];
        b0 = q[0]; b1 = q[1]; b2 = tq < 2 ? q[2] : make_uint2(0u, 0u);
    }
#pragma unroll 1
    for (int par = 0; par < 2; par++) {
        const uint32_t dK = uni((((sbase + (par ? 2048 : 6144)) & 0x3FFFF) >> 4) | ((2048u >> 4) << 16));
        const uint32_t ksoff = par ? 0 : 10240;
        const uint32_t dS = uni((((sbase + ksoff) & 0x3FFFF) >> 4) | (((K2_STAGES * KV_BYTES - ksoff) >> 4) << 16));
        const uint32_t dV = uni((((sbase + (par ? 6144 : 0)) & 0x3FFFF) >> 4) | ((128u >> 4) << 16));
        const bool isdata = par ? (tq >= 2) : (tq < 2);
        const bool fast = __all_sync(~0u, (fastbits >> par) & 1);
        float o[12];
#pragma unroll
        for (int i = 0; i < 12; i++) o[i] = 0.f;
        if (fast) {
#pragma unroll 4
            for (int t = par * 16; t < par * 16 + 16; t++) {
                const uint32_t st = t & 3, so = st * (KV_BYTES >> 4);
                const uint64_t kd = mk64(dK + so, 8), sd = mk64(dS + st * ((KV_BYTES >> 4) * (1u - 65536u)), 8), vd = mk64(dV + so, 128);
                const uint32_t fbar = full0 + 8 * st;
                mbar_spin(fbar, (t >> 2) & 1);
#pragma unroll
                for (int hf = 0; hf < 2; hf++) {
                    float s[32];
                    wg_fence();
                    qk_mma<0>(s, b0.x, b0.y, b1.x, b1.y, kd + hf * 64);
                    qk_mma<1>(s, b2.x, b2.y, e0, e1, sd + hf * 64);
                    wg_commit();
                    if (hf == 1 && st == ldsel) side_jobs(t);
                    wg_wait<0>();
                    if (hf == 0 && lane == 0) mbar_arrive(relbar);
                    uint32_t p[16];
#pragma unroll
                    for (int g = 0; g < 2; g++) {
                        fence_regs(s);
#pragma unroll
                        for (int b = g * 4; b < g * 4 + 4; b++)
                            if (!((POLYMASK >> (b + hf * 8)) & 1)) {
#pragma unroll
                                for (int i = 0; i < 4; i++) asm volatile("ex2.approx.ftz.f32 %0, %0;" : "+f"(s[4 * b + i]));
                            }
                        fence_regs(s);
#pragma unroll
                        for (int b = g * 4; b < g * 4 + 4; b++)
                            if ((POLYMASK >> (b + hf * 8)) & 1) {
                                p[2 * b] = ex2_pk(s[4 * b], s[4 * b + 1]);
                                p[2 * b + 1] = ex2_pk(s[4 * b + 2], s[4 * b + 3]);
                            }
#pragma unroll
                        for (int b = g * 4; b < g * 4 + 4; b++)
                            if (!((POLYMASK >> (b + hf * 8)) & 1)) {
                                p[2 * b] = pack_bf16(s[4 * b], s[4 * b + 1]);
                                p[2 * b + 1] = pack_bf16(s[4 * b + 2], s[4 * b + 3]);
                            }
#pragma unroll
                        for (int i = g * 8; i < g * 8 + 8; i++) asm volatile("" : "+r"(p[i]) :: "memory");
                        wg_fence();
#pragma unroll
                        for (int k = g * 2; k < g * 2 + 2; k++) pv_mma(o, p[4 * k], p[4 * k + 1], p[4 * k + 2], p[4 * k + 3], vd + (hf * 4 + k) * 16);
                    }
                    wg_commit();
                }
                relbar = fbar + 8 * K2_STAGES;
            }
        } else {
            float m0 = -INFINITY, m1 = -INFINITY;
#pragma unroll 1
            for (int hh = 0; hh < 32; hh++) {
                const int t = par * 16 + (hh >> 1), st = t % K2_STAGES, hf = hh & 1;
                if (!hf) mbar_spin(full0 + 8 * st, (t / K2_STAGES) & 1);
                float s[32];
                wg_fence();
                wgmma_rs_n64_tb0<8, 0>(s, b0.x, b0.y, b1.x, b1.y, dK + ((st * KV_BYTES + hf * 1024) >> 4));
                wgmma_rs_n64_tb0<8, 1>(s, b2.x, b2.y, e0, e1, dS + ((st * KV_BYTES + hf * 1024) >> 4) - (((st * KV_BYTES) >> 4) << 16));
                wg_commit();
                wg_wait<0>();
                fence_regs(s); fence_regs(o);
                if (!hf && lane == 0) mbar_arrive(relbar);
                if (hf) { relbar = empty0 + 8 * st; if (st == ldsel) side_jobs(t); }
                float x0 = m0, x1 = m1;
#pragma unroll
                for (int b = 0; b < 8; b++) {
                    x0 = fmaxf(x0, fmaxf(s[4 * b], s[4 * b + 1]));
                    x1 = fmaxf(x1, fmaxf(s[4 * b + 2], s[4 * b + 3]));
                }
                x0 = fmaxf(x0, __shfl_xor_sync(~0u, x0, 1)); x0 = fmaxf(x0, __shfl_xor_sync(~0u, x0, 2));
                x1 = fmaxf(x1, __shfl_xor_sync(~0u, x1, 1)); x1 = fmaxf(x1, __shfl_xor_sync(~0u, x1, 2));
                const float c0 = ex2(m0 - x0), c1 = ex2(m1 - x1);
                m0 = x0; m1 = x1;
#pragma unroll
                for (int b = 0; b < 3; b++) { o[4 * b] *= c0; o[4 * b + 1] *= c0; o[4 * b + 2] *= c1; o[4 * b + 3] *= c1; }
                uint32_t p[16];
#pragma unroll
                for (int b = 0; b < 8; b++) {
                    p[2 * b] = pack_bf16(ex2(s[4 * b] - m0), ex2(s[4 * b + 1] - m0));
                    p[2 * b + 1] = pack_bf16(ex2(s[4 * b + 2] - m1), ex2(s[4 * b + 3] - m1));
                }
                fence_regs(p); fence_regs(o);
                wg_fence();
#pragma unroll
                for (int k = 0; k < 4; k++)
                    wgmma_rs_n24_tb1<128, 1>(o, p[4 * k], p[4 * k + 1], p[4 * k + 2], p[4 * k + 3], dV + ((st * KV_BYTES + (hf * 4 + k) * 256) >> 4));
                wg_commit();
                wg_wait<0>();
            }
        }
        const uint2 nb0 = make_uint2(__ldcg(qp + 3 * 512), __ldcg(qp + 3 * 512 + 32)), nb1 = make_uint2(__ldcg(qp + 4 * 512), __ldcg(qp + 4 * 512 + 32));
        const uint2 nb2 = make_uint2(__ldcg(qp + 2 * 512), __ldcg(qp + 2 * 512 + 32));
        const int rloc = (rt & 1) * 64 + (t128 >> 5) * 16 + (lane >> 2);
        const float gt0 = __ldcg(g_gate + (rt >> 1) * 128 + rloc), gt1 = __ldcg(g_gate + (rt >> 1) * 128 + rloc + 8);
        wg_wait<0>();
        fence_regs(o);
        const int src = (lane & ~3) | (par ? 0 : 2);
        const float l0 = __shfl_sync(~0u, o[8], src), l1 = __shfl_sync(~0u, o[10], src);
        const float i0 = gt0 / l0, i1 = gt1 / l1;
        uint32_t* ob = (uint32_t*)g_o + ((size_t)(rt >> 1) * 80 * 128 + rloc) * 4;
        const int cb = par * 320 + hp * 20 + tq * 2;
#pragma unroll
        for (int b = 0; b < 3; b++) {
            const int col = cb + (par ? (b == 2 ? -4 : 4 + b * 8) : b * 8);
            uint32_t* d = ob + (col >> 3) * 512 + ((col & 7) >> 1);
            if (b < 2 || isdata) {
                d[0] = pack_bf16(o[4 * b] * i0, o[4 * b + 1] * i0);
                d[32] = pack_bf16(o[4 * b + 2] * i1, o[4 * b + 3] * i1);
            }
        }
        __syncwarp();
        if (par == 1) {
            unsigned int* cp = g_cnt_o2 + (rt >> 1) * 8 + (hp * 20 >> 6);
            const int two = (hp * 20 >> 6) != ((hp * 20 + 19) >> 6);
            asm volatile("{\n.reg .pred p, q;\nelect.sync _|p, 0xffffffff;\nsetp.ne.and.s32 q, %1, 0, p;\n@p red.release.gpu.global.add.u32 [%0], 1;\n"
                         "@q red.release.gpu.global.add.u32 [%0+4], 1;\n}" :: "l"(cp), "r"(two) : "memory");
        }
        else mbar_arrive_e(empty0 + 8 * K2_STAGES);
        b0 = nb0; b1 = nb1; b2 = tq >= 2 ? nb2 : make_uint2(0u, 0u); e0 = e0n; e1 = e1n;
    }
}

constexpr int K3_S = 16384 + 10240;
constexpr int K3_SMEM = 6 * K3_S + 256;

__device__ __forceinline__ void out_mma(float (&d)[40], uint64_t da, uint64_t db, int scale_d) {
  asm volatile("{\n.reg .pred p;\nsetp.ne.b32 p, %42, 0;\n"
  "wgmma.mma_async.sync.aligned.m64n80k16.f32.bf16.bf16 {%0, %1, %2, %3, %4, %5, %6, %7, %8, %9, %10, %11, %12, %13, %14, %15, %16, %17, %18, %19, %20, %21, %22, %23, %24, %25, %26, %27, %28, %29, %30, %31, %32, %33, %34, %35, %36, %37, %38, %39}, %40, %41, p, 1, 1, 0, 1;\n}\n"
  : "+f"(d[0]), "+f"(d[1]), "+f"(d[2]), "+f"(d[3]), "+f"(d[4]), "+f"(d[5]), "+f"(d[6]), "+f"(d[7]), "+f"(d[8]), "+f"(d[9]), "+f"(d[10]), "+f"(d[11]), "+f"(d[12]), "+f"(d[13]), "+f"(d[14]), "+f"(d[15]), "+f"(d[16]), "+f"(d[17]), "+f"(d[18]), "+f"(d[19]), "+f"(d[20]), "+f"(d[21]), "+f"(d[22]), "+f"(d[23]), "+f"(d[24]), "+f"(d[25]), "+f"(d[26]), "+f"(d[27]), "+f"(d[28]), "+f"(d[29]), "+f"(d[30]), "+f"(d[31]), "+f"(d[32]), "+f"(d[33]), "+f"(d[34]), "+f"(d[35]), "+f"(d[36]), "+f"(d[37]), "+f"(d[38]), "+f"(d[39])
  : "l"(da), "l"(db), "r"(scale_d));
}

__global__ void __launch_bounds__(128, 4)
k3_out(const __grid_constant__ CUtensorMap tm_out, const __nv_bfloat16* __restrict__ b2) {
    extern __shared__ __align__(1024) uint8_t smem_raw[];
    const uint32_t sbase = smem_u32(smem_raw);
    const uint32_t full0 = sbase + 6 * K3_S, done0 = full0 + 48;
    const int tid = threadIdx.x, lane = tid & 31, tq = lane & 3;
    const int warp = __shfl_sync(~0u, tid >> 5, 0);
    const int c = blockIdx.x >> 3, r = blockIdx.x & 7;
    const uint32_t epoch = uni(*(volatile unsigned int*)&g_done >> 7);
    const uint4* ah = g_h + (size_t)c * 216 * 128;
    const uint4* ao = g_o + (size_t)c * 80 * 128 - 27 * 1024;
    const uint4* bw = g_wp + (size_t)r * 37 * 640;
    auto loadA = [&](int it, uint32_t sl) {
        mbar_expect_e(full0 + 8 * sl, 16384);
        bulk_g2s(sbase + sl * K3_S, (it < 27 ? ah : ao) + it * 1024, 16384, full0 + 8 * sl);
    };
    auto loadB = [&](int it, uint32_t sl) {
        mbar_expect_e(full0 + 8 * sl, 10240);
        bulk_g2s(sbase + sl * K3_S + 16384, bw + it * 640, 10240, full0 + 8 * sl);
    };
    if (warp == 0) {
        if (lane < 12) mbar_init(full0 + 8 * lane, lane < 6 ? 2 : 4);
        asm volatile("fence.mbarrier_init.release.cluster;" ::: "memory");
        __syncwarp();
#pragma unroll 1
        for (int i = 0; i < 6; i++) { loadA(i, i); loadB(i, i); }
    }
    __syncthreads();
    const uint32_t dA = uni(((sbase & 0x3FFFF) >> 4) | ((2048u >> 4) << 16));
    const uint32_t dB = uni((((sbase + 16384) & 0x3FFFF) >> 4) | ((128u >> 4) << 16));
    float acc0[40], acc1[40];
    uint32_t sl = 0, ph = 0, sl1 = 0, ph1 = 0, sl2 = 0, ph2 = 0;
    uint32_t todo = 31;
#pragma unroll 1
    for (int it = 0; it < 37; it++) {
        if (it == 27) {
            wg_wait<0>();
            fence_regs(acc0); fence_regs(acc1);
            __syncthreads();
            if (warp == 0) {
                wait_count(g_cnt_o + c, (epoch + 1) * 128);
#pragma unroll 1
                for (int i = 27; i < 32; i++) loadA(i, i % 6);
            }
            const float* gp = g_gate + c * 128 + warp * 16 + (lane >> 2);
            const float w0 = 1.f - __ldcg(gp), w1 = 1.f - __ldcg(gp + 8), w2 = 1.f - __ldcg(gp + 64), w3 = 1.f - __ldcg(gp + 72);
            const uint32_t* bp = (const uint32_t*)(b2 + r * 80) + tq;
#pragma unroll
            for (int j = 0; j < 10; j++) {
                const uint32_t bb = __ldg(bp + j * 4);
                const float bl = bf_lo(bb), bh = bf_hi(bb);
                acc0[4 * j] = (acc0[4 * j] + bl) * w0; acc0[4 * j + 1] = (acc0[4 * j + 1] + bh) * w0;
                acc0[4 * j + 2] = (acc0[4 * j + 2] + bl) * w1; acc0[4 * j + 3] = (acc0[4 * j + 3] + bh) * w1;
                acc1[4 * j] = (acc1[4 * j] + bl) * w2; acc1[4 * j + 1] = (acc1[4 * j + 1] + bh) * w2;
                acc1[4 * j + 2] = (acc1[4 * j + 2] + bl) * w3; acc1[4 * j + 3] = (acc1[4 * j + 3] + bh) * w3;
            }
            fence_regs(acc0); fence_regs(acc1);
        }
        if (it >= 32) {
            if (it == 32) {
                wg_wait<0>();
                __syncthreads();
                if (warp == 1) loadB(36, 0);
            }
            if (warp == 0) {
                uint32_t n = 0;
                while ((todo >> (it - 32)) & 1) {
                    uint32_t v;
                    asm volatile("ld.acquire.gpu.global.u32 %0, [%1];" : "=r"(v) : "l"(g_cnt_o2 + c * 8 + (lane & 7)) : "memory");
                    uint32_t ready = __ballot_sync(~0u, (int)(v - (epoch + 1) * 32) >= 0) & todo;
                    if (!ready) {
                        __nanosleep(100);
                        if (++n > 8000000u) __trap();
                        continue;
                    }
                    asm volatile("fence.proxy.async.global;" ::: "memory");
                    todo &= ~ready;
                    while (ready) {
                        const int blk = __ffs(ready) - 1;
                        ready &= ready - 1;
                        loadA(32 + blk, blk == 4 ? 0 : blk + 2);
                    }
                }
            }
        }
        if (it == 27 || it == 32) mbar_wait(full0 + 8 * sl, ph); else mbar_spin(full0 + 8 * sl, ph);
        const uint64_t da = mk64(dA + sl * (K3_S >> 4), 128u >> 4), db = mk64(dB + sl * (K3_S >> 4), 1024u >> 4);
        wg_fence();
#pragma unroll
        for (int k = 0; k < 4; k++) {
            out_mma(acc0, da + k * (4096 >> 4), db + k * (256 >> 4), (it | k) != 0);
            out_mma(acc1, da + k * (4096 >> 4) + (1024 >> 4), db + k * (256 >> 4), (it | k) != 0);
        }
        wg_commit();
        if (it < 32) {
            if (it >= 2 && warp == (it & 3)) {
                mbar_spin(done0 + 8 * sl2, ph2);
                loadB(it + 4, sl2);
                if (it + 4 < 27) loadA(it + 4, sl2);
            }
            wg_wait<1>();
            if (it > 0) mbar_arrive_e(done0 + 8 * sl1);
            sl2 = sl1; ph2 = ph1; sl1 = sl; ph1 = ph;
        }
        if (++sl == 6) { sl = 0; ph ^= 1; }
    }
    wg_wait<0>();
    fence_regs(acc0); fence_regs(acc1);
    const uint32_t stg0 = sbase + K3_S, stg1 = stg0 + 10240;
    {
        const uint32_t ro = (warp * 16 + (lane & 15)) * 160 + (lane >> 4) * 16;
#pragma unroll
        for (int j = 0; j < 5; j++) {
            stsm4(stg0 + ro + j * 32, pack_bf16(acc0[8 * j], acc0[8 * j + 1]), pack_bf16(acc0[8 * j + 2], acc0[8 * j + 3]),
                  pack_bf16(acc0[8 * j + 4], acc0[8 * j + 5]), pack_bf16(acc0[8 * j + 6], acc0[8 * j + 7]));
            stsm4(stg1 + ro + j * 32, pack_bf16(acc1[8 * j], acc1[8 * j + 1]), pack_bf16(acc1[8 * j + 2], acc1[8 * j + 3]),
                  pack_bf16(acc1[8 * j + 4], acc1[8 * j + 5]), pack_bf16(acc1[8 * j + 6], acc1[8 * j + 7]));
        }
    }
    fence_async_smem();
    __syncwarp();
    asm volatile("{\n.reg .pred p;\nelect.sync _|p, 0xffffffff;\n"
                 "@p cp.async.bulk.tensor.2d.global.shared::cta.bulk_group [%0, {%1, %2}], [%4];\n"
                 "@p cp.async.bulk.tensor.2d.global.shared::cta.bulk_group [%0, {%1, %3}], [%5];\n"
                 "cp.async.bulk.commit_group;\n"
                 "cp.async.bulk.wait_group.read 0;\n}"
                 :: "l"(&tm_out), "r"(r * 80), "r"(c * 128 + warp * 16), "r"(c * 128 + 64 + warp * 16),
                    "r"(stg0 + warp * 2560), "r"(stg1 + warp * 2560) : "memory");
    if (tid == 0) atomicAdd(&g_done, 1u);
}

typedef CUresult (*EncodeFn)(CUtensorMap*, CUtensorMapDataType, cuuint32_t, void*, const cuuint64_t*, const cuuint64_t*,
                             const cuuint32_t*, const cuuint32_t*, CUtensorMapInterleave, CUtensorMapSwizzle,
                             CUtensorMapL2promotion, CUtensorMapFloatOOBfill);

static void make_map(EncodeFn enc, CUtensorMap* m, const void* p, int rank, const cuuint64_t* dims, const cuuint64_t* strides,
                     const cuuint32_t* box, CUtensorMapSwizzle sw) {
    cuuint32_t es[2] = {1, 1};
    enc(m, CU_TENSOR_MAP_DATA_TYPE_BFLOAT16, rank, (void*)p, dims, strides, box, es, CU_TENSOR_MAP_INTERLEAVE_NONE, sw,
        CU_TENSOR_MAP_L2_PROMOTION_L2_256B, CU_TENSOR_MAP_FLOAT_OOB_FILL_NONE);
}

template<typename... KArgs, typename... Args>
static void launch(void (*kern)(KArgs...), int grid, int block, int smem, bool pdl, Args... args) {
    cudaLaunchConfig_t cfg = {};
    cfg.gridDim = dim3(grid); cfg.blockDim = dim3(block); cfg.dynamicSmemBytes = smem; cfg.stream = cudaStreamPerThread;
    cudaLaunchAttribute at[1];
    at[0].id = cudaLaunchAttributeProgrammaticStreamSerialization;
    at[0].val.programmaticStreamSerializationAllowed = 1;
    cfg.attrs = at; cfg.numAttrs = pdl ? 1 : 0;
    cudaLaunchKernelEx(&cfg, kern, args...);
}

extern "C" void kernel_launch(void* const* d_in, const int* in_sizes, int n_in, void* d_out, int out_size) {
    const __nv_bfloat16* x = (const __nv_bfloat16*)d_in[0];
    const __nv_bfloat16* wqkv = (const __nv_bfloat16*)d_in[1];
    const __nv_bfloat16* wo = (const __nv_bfloat16*)d_in[2];
    const __nv_bfloat16* w1 = (const __nv_bfloat16*)d_in[4];
    const __nv_bfloat16* b1 = (const __nv_bfloat16*)d_in[5];
    const __nv_bfloat16* w2 = (const __nv_bfloat16*)d_in[6];
    const __nv_bfloat16* b2 = (const __nv_bfloat16*)d_in[7];
    const __nv_bfloat16* gate_w = (const __nv_bfloat16*)d_in[8];
    __nv_bfloat16* out = (__nv_bfloat16*)d_out;

    void* fn = nullptr;
    cudaDriverEntryPointQueryResult qr;
    cudaGetDriverEntryPoint("cuTensorMapEncodeTiled", &fn, cudaEnableDefault, &qr);
    EncodeFn enc = (EncodeFn)fn;
    CUtensorMap tm_x, tm_wqkv, tm_w1, tm_out;
    {
        cuuint64_t d[2] = {DM, SEQ}, s[1] = {DM * 2}; cuuint32_t b[2] = {32, 128}, b3[2] = {80, 16};
        make_map(enc, &tm_x, x, 2, d, s, b, CU_TENSOR_MAP_SWIZZLE_64B);
        make_map(enc, &tm_out, out, 2, d, s, b3, CU_TENSOR_MAP_SWIZZLE_NONE);
    }
    {
        cuuint64_t d[2] = {3 * DM, DM}, s[1] = {3 * DM * 2}; cuuint32_t b[2] = {64, 32};
        make_map(enc, &tm_wqkv, wqkv, 2, d, s, b, CU_TENSOR_MAP_SWIZZLE_128B);
    }
    {
        cuuint64_t d[2] = {FF, DM}, s[1] = {FF * 2}; cuuint32_t b[2] = {64, 32};
        make_map(enc, &tm_w1, w1, 2, d, s, b, CU_TENSOR_MAP_SWIZZLE_128B);
    }
    cudaFuncSetAttribute(k1_gemm, cudaFuncAttributeMaxDynamicSharedMemorySize, K1_SMEM);
    cudaFuncSetAttribute(k2_attn, cudaFuncAttributeMaxDynamicSharedMemorySize, K2_SMEM);
    cudaFuncSetAttribute(k3_out, cudaFuncAttributeMaxDynamicSharedMemorySize, K3_SMEM);
    cudaFuncSetAttribute(k2_attn, cudaFuncAttributePreferredSharedMemoryCarveout, 100);
    cudaFuncSetAttribute(k3_out, cudaFuncAttributePreferredSharedMemoryCarveout, 100);

    launch(k1_gemm, 132, 384, K1_SMEM, false, tm_x, tm_wqkv, tm_w1, x, gate_w, b1, w2, wo);
    launch(k2_attn, 128, 512, K2_SMEM, true);
    launch(k3_out, 128, 128, K3_SMEM, true, tm_out, b2);
}
```
